```python
import torch

def _softmax(x, axis=-1):
    return torch.softmax(x, dim=axis)
def _gelu(x):
    return torch.nn.functional.gelu(x, approximate="tanh")
def _silu(x):
    return torch.nn.functional.silu(x)
def _sigmoid(x):
    return torch.sigmoid(x)
def _layernorm(x, axis=-1, eps=1e-5):
    m = x.mean(dim=axis, keepdim=True)
    v = x.var(dim=axis, keepdim=True, unbiased=False)
    return (x - m) / torch.sqrt(v + eps)
def _scatter_add(tgt, idx, src, axis=0):
    return tgt.clone().index_add_(axis, idx, src)
def _segment_sum(src, seg, n):
    out = torch.zeros((n,) + src.shape[1:], dtype=src.dtype)
    return out.index_add_(0, seg, src)
def _pad(x, pw):
    flat = tuple(v for pair in reversed(pw) for v in pair)
    return torch.nn.functional.pad(x, flat)

kernel_name = 'gated_mix__ssm_conv_s4__dense_activation_squared_relu__prompt'

def setup_inputs():

    _w = (lambda a: (lambda t: t.to(torch.bfloat16) if t.is_floating_point() else t)(torch.as_tensor(a)))
    def _A_setup():
        B, L, D, N = 1, 2048, 640, 192
        A_re = -(lambda _x: torch.exp(torch.as_tensor(_x)))((lambda *s: torch.randn(*s, dtype=torch.bfloat16) * 6.4)(D, N))
        A_im = torch.pi * (lambda *s: torch.randn(*s, dtype=torch.bfloat16) * 0.1)(D, N)
        B_re = (lambda *s: torch.randn(*s, dtype=torch.bfloat16) * 0.2)(D, N)
        B_im = (lambda *s: torch.randn(*s, dtype=torch.bfloat16) * 0.2)(D, N)
        C_re = (lambda *s: torch.randn(*s, dtype=torch.bfloat16) * 0.2)(D, N)
        C_im = (lambda *s: torch.randn(*s, dtype=torch.bfloat16) * 0.2)(D, N)
        log_dt = (lambda *s: torch.randn(*s, dtype=torch.bfloat16) * 0.1)(D) * 0.5 - 4.0
        Dskip = (lambda *s: torch.randn(*s, dtype=torch.bfloat16) * 0.1)(D)
        return {
            "u": _w((lambda *s: torch.randn(*s, dtype=torch.bfloat16) * 0.05)(B, L, D)),
            "A_re": _w(A_re),
            "A_im": _w(A_im),
            "B_re": _w(B_re),
            "B_im": _w(B_im),
            "C_re": _w(C_re),
            "C_im": _w(C_im),
            "log_dt": _w(log_dt),
            "Dskip": _w(Dskip),
        }
    _A_in = _A_setup()

    def _B_setup():
        B, S, D, F = 1, 2048, 640, 1536
        return {
            "x": _w((lambda *s: torch.randn(*s, dtype=torch.bfloat16) * 0.05)(B, S, D)),
            "w1": _w((lambda *s: torch.randn(*s, dtype=torch.bfloat16) * 0.05)(D, F)),
            "b1": _w((lambda *s: torch.randn(*s, dtype=torch.bfloat16) * 0.05)(F)),
            "w2": _w((lambda *s: torch.randn(*s, dtype=torch.bfloat16) * 0.05)(F, D)),
            "b2": _w((lambda *s: torch.randn(*s, dtype=torch.bfloat16) * 0.05)(D)),
        }
    _B_in = _B_setup()

    return {
        "A_u": _A_in["u"],
        "A_A_re": _A_in["A_re"],
        "A_A_im": _A_in["A_im"],
        "A_B_re": _A_in["B_re"],
        "A_B_im": _A_in["B_im"],
        "A_C_re": _A_in["C_re"],
        "A_C_im": _A_in["C_im"],
        "A_log_dt": _A_in["log_dt"],
        "A_Dskip": _A_in["Dskip"],
        "B_x": _B_in["x"],
        "B_w1": _B_in["w1"],
        "B_b1": _B_in["b1"],
        "B_w2": _B_in["w2"],
        "B_b2": _B_in["b2"],
        "gate_w": _w((lambda *s: torch.randn(*s, dtype=torch.bfloat16) * 0.05)(640) * 16.0),
    }

def reference(A_u, A_A_re, A_A_im, A_B_re, A_B_im, A_C_re, A_C_im, A_log_dt, A_Dskip, B_x, B_w1, B_b1, B_w2, B_b2, gate_w):
    def _A_ref(u, A_re, A_im, B_re, B_im, C_re, C_im, log_dt, Dskip):
        Bsz, L, D = u.shape
        dt = torch.exp(log_dt)[:, None]
        A = A_re + 1j * A_im
        Bc = B_re + 1j * B_im
        Cc = C_re + 1j * C_im
        logdA = dt * A
        dB = dt * Bc
        l = (lambda x, dt: x.to(dt))(torch.arange(L), A_re.dtype)
        P = torch.exp(logdA[:, :, None] * l[None, None, :])
        K = torch.einsum("dn,dnl,dn->dl", Cc, P, dB).real
        L2 = 2 * L
        Kp = _pad(K, ((0, 0), (0, L)))
        up = (lambda x, *d: x.permute(*d))(u, 0, 2, 1)
        up = _pad(up, ((0, 0), (0, 0), (0, L)))
        Kf = (lambda x, axes=(-2,-1): torch.fft.rfft2(x.float(), dim=axes))(Kp[:, None, :], axes=(-2, -1))
        Uf = (lambda x, axes=(-2,-1): torch.fft.rfft2(x.float(), dim=axes))(up[:, :, None, :], axes=(-2, -1))
        Yf = Uf * Kf[None, :, :, :]
        y = (lambda x, s, axes=(-2,-1): torch.fft.irfft2(x, s=s, dim=axes).to(torch.bfloat16))(Yf, (1, L2), axes=(-2, -1))[:, :, 0, :L]
        y = (lambda x, *d: x.permute(*d))(y, 0, 2, 1) + u * Dskip[None, None, :]
        return y

    def _B_ref(x, w1, b1, w2, b2):
        h = torch.einsum("bsd,df->bsf", x, w1) + b1
        zero = torch.zeros_like(h)
        r = torch.where(h > zero, h, zero)
        h = r * r
        out = torch.einsum("bsf,fd->bsd", h, w2) + b2
        return out

    x = A_u
    g = _sigmoid((x * gate_w).sum(-1, keepdims=True))
    a = _A_ref(x, A_A_re, A_A_im, A_B_re, A_B_im, A_C_re, A_C_im, A_log_dt, A_Dskip)
    b = _B_ref(x, B_w1, B_b1, B_w2, B_b2)
    return g * a + (1 - g) * b
```

```cpp
#include <cuda_runtime.h>
#include <cuda_bf16.h>
#include <cuda_fp16.h>
#include <cuda.h>
#include <stdint.h>

namespace {

#define PRI 4
#define ORD 1
#define PRIK 0
#define FINB 1
#define PRIL 0
constexpr int SEQ = 2048, DM = 640, NST = 192, FF = 1536;
constexpr int NCTA = 128, NTHREADS = 512;
#define REG_SSM 168
#define REG_CTL 88
#define SPLIT 4
#define EARLY2 0
#define GATE_FIN 20

constexpr int STAGE_BYTES = 40960, NSTAGE = 3;
constexpr int UC_C     = 1184;
constexpr int UC_CHB   = 4 * UC_C;
constexpr int OFF_X    = NSTAGE * STAGE_BYTES;
constexpr int OFF_KC   = OFF_X;
constexpr int KC_CHB   = 1696;
constexpr int OFF_SOUT = OFF_X + 9216;
constexpr int OFF_WORK = OFF_X + 20480;
constexpr int SLOT     = 7168;
constexpr int OFF_UC   = OFF_WORK + 12 * SLOT - 5 * UC_CHB;
constexpr int OFF_BAR  = OFF_WORK + 12 * SLOT;
constexpr int OFF_GOUT = OFF_BAR + 384;
constexpr int OFF_B2   = OFF_GOUT + 256;
constexpr int OFF_SC   = OFF_B2 + 320;
constexpr int OFF_GW   = OFF_SC + 128;
constexpr int OFF_TS   = OFF_GW + 1280;
constexpr int SMEM_BYTES = OFF_TS + 512;
static_assert(SMEM_BYTES <= 232448, "smem");
constexpr int TA01_B = 41 * 288, TA2 = TA01_B, TA3 = TA2 + 2 * 3168, YC = 1056, Y2 = TA3 + 2 * 2016, Y3 = Y2 + 4 * YC,
              W5 = Y3 + 4 * YC, W3 = W5 + 3584, W9 = W3 + 3584, W7 = W9 + 2048, WC = W7 + 2048, WD1 = -7168 - W5, WD2 = 6144,
              TA01A = WC + 2048 + WD2;
static_assert(OFF_WORK + TA01A + TA01_B <= OFF_UC && W9 + WD2 >= 6 * SLOT, "work");
constexpr int OFF_Q    = STAGE_BYTES;
constexpr int OFF_AT   = OFF_WORK + 40960;
constexpr int OFF_OUT  = OFF_X;
static_assert(OFF_AT % 1024 == 0, "reuse");
constexpr int B_FULL = 0, B_UTILE = 3, B_AT = 4, B_SSMDONE = 5, B_PEERFREE = 6, B_HST = 7, B_URDY = 10, B_TFREE = 11,
              B_KF = 12, B_KE = 15, B_UFULL = 17, B_WF = 18, B_RED = 20, B_WE = 21, B_OUT = 22, B_WG = 23, B_G = 24, B_PRI = 25, NBAR = 26;
constexpr int bar_count(int i) {
  return i >= B_HST && i < B_HST + 3 ? 8 : i == B_TFREE ? 3 : i == B_PEERFREE ? 8 : i >= B_G ? 1 : i == B_KF + 2 ? 6 : i >= B_KF && i < B_KE ? 12 :
         i >= B_KE && i < B_UFULL ? 4 : (i >= B_WF && i < B_RED) || i == B_WG ? 2 : i >= B_WE ? 4 : 1;
}
constexpr uint64_t bar_tab(int i, int n) { return n == 0 ? 0 : (uint64_t)bar_count(i) | (bar_tab(i + 1, n - 1) << 4); }
constexpr uint64_t BAR_T0 = bar_tab(4, 12), BAR_T1 = bar_tab(16, 10);

__device__ __align__(1024) uint8_t g_uT[DM * UC_CHB];
__device__ unsigned g_uflag[16 * 32];
__device__ __align__(1024) __nv_bfloat16 g_h[SEQ * FF];
__device__ __align__(1024) __nv_bfloat16 g_aT[DM * SEQ];
__device__ __align__(1024) float g_gate[4 * SEQ];
__device__ unsigned g_hflag[384 * 8];
__device__ unsigned g_aflag[4 * 32];
__device__ unsigned g_epoch[(NCTA + 4) * 8];
#define TSP(r, i)
#define TSPDUMP()
#define TS(i)
#define TSDUMP()
#define TSINIT()

#define TSD(i)
#define TSH(i)
#define TSW(i)
#define TSV(i)
#define TSHDUMP()
struct Params {
  const __nv_bfloat16 *x, *Are, *Aim, *Bre, *Bim, *Cre, *Cim, *logdt, *Dskip, *b1, *b2, *gw, *w2, *w1;
  int use_smid;
};

__device__ __forceinline__ uint32_t smem_u32(const void* p) { return (uint32_t)__cvta_generic_to_shared(p); }
__device__ __forceinline__ void mbar_init(uint32_t bar, uint32_t cnt) {
  asm volatile("mbarrier.init.shared::cta.b64 [%0], %1;" ::"r"(bar), "r"(cnt) : "memory");
}
__device__ __forceinline__ void mbar_expect_tx(uint32_t bar, uint32_t bytes) {
  asm volatile("mbarrier.arrive.expect_tx.shared::cta.b64 _, [%0], %1;" ::"r"(bar), "r"(bytes) : "memory");
}
__device__ __forceinline__ void mbar_arrive(uint32_t bar) {
  asm volatile("mbarrier.arrive.shared::cta.b64 _, [%0];" ::"r"(bar) : "memory");
}
__device__ __forceinline__ void mbar_arrive_remote(uint32_t cluster_addr) {
  asm volatile("mbarrier.arrive.relaxed.cluster.shared::cluster.b64 _, [%0];" ::"r"(cluster_addr) : "memory");
}
__device__ __forceinline__ bool mbar_try(uint32_t bar, uint32_t parity) {
  uint32_t ok;
  asm volatile("{\n.reg .pred p;\nmbarrier.try_wait.parity.shared::cta.b64 p, [%1], %2;\nselp.u32 %0, 1, 0, p;\n}\n"
               : "=r"(ok) : "r"(bar), "r"(parity) : "memory");
  return ok != 0;
}
__device__ __forceinline__ uint32_t mbar_test1(uint32_t bar, uint32_t parity) {
  uint32_t ok;
  asm volatile("{\n.reg .pred p;\nmbarrier.test_wait.parity.shared::cta.b64 p, [%1], %2;\nselp.u32 %0, 1, 0, p;\n}\n"
               : "=r"(ok) : "r"(bar), "r"(parity) : "memory");
  return ok;
}
__device__ __forceinline__ bool mbar_test(uint32_t bar, uint32_t parity) {
  return __shfl_sync(0xffffffffu, mbar_test1(bar, parity), 0) != 0;
}
__device__ __forceinline__ void mbar_wait(uint32_t bar, uint32_t parity) {
#pragma unroll 1
  for (uint32_t n = 0; n < (1u << 20) && !mbar_try(bar, parity); n++) {}
}
__device__ __forceinline__ unsigned ld_relaxed(const unsigned* f) {
  unsigned v;
  asm volatile("ld.relaxed.gpu.global.u32 %0, [%1];" : "=r"(v) : "l"(f) : "memory");
  return v;
}
__device__ __forceinline__ void flag_wait(const unsigned* f, unsigned target) {
#pragma unroll 1
  for (uint32_t n = 0; n < (1u << 20) && (int)(ld_relaxed(f) - target) < 0; n++) {}
}
__device__ __forceinline__ bool flag_try(const unsigned* f, unsigned target) { return (int)(ld_relaxed(f) - target) >= 0; }
__device__ __forceinline__ void flag_add(unsigned* f) {
  asm volatile("red.relaxed.gpu.global.add.u32 [%0], 1;" ::"l"(f) : "memory");
}
__device__ __forceinline__ uint32_t atom_add(uint32_t a, uint32_t v) {
  uint32_t r;
  asm volatile("atom.relaxed.cta.shared.add.u32 %0, [%1], %2;" : "=r"(r) : "r"(a), "r"(v) : "memory");
  return r;
}
__device__ __forceinline__ void st_async128(uint32_t a, float x, float y, float z, float w, uint32_t bar) {
  asm volatile("st.async.weak.shared::cluster.mbarrier::complete_tx::bytes.v4.f32 [%0], {%1,%2,%3,%4}, [%5];"
               ::"r"(a), "f"(x), "f"(y), "f"(z), "f"(w), "r"(bar) : "memory");
}
__device__ __forceinline__ uint32_t mapa(uint32_t a, uint32_t rank) {
  uint32_t r; asm volatile("mapa.shared::cluster.u32 %0, %1, %2;" : "=r"(r) : "r"(a), "r"(rank)); return r;
}
__device__ __forceinline__ void fence_async_smem() { asm volatile("fence.proxy.async.shared::cta;" ::: "memory"); }
__device__ __forceinline__ void bar_sync(int id, int n) { asm volatile("bar.sync %0, %1;" ::"r"(id), "r"(n) : "memory"); }
__device__ __forceinline__ void bar_arrive(int id, int n) { asm volatile("bar.arrive %0, %1;" ::"r"(id), "r"(n) : "memory"); }
__device__ __forceinline__ void tma2d(uint32_t dst, const CUtensorMap* tm, uint32_t bar, int c0, int c1) {
  asm volatile("cp.async.bulk.tensor.2d.shared::cluster.global.mbarrier::complete_tx::bytes [%0], [%1, {%3, %4}], [%2];"
               ::"r"(dst), "l"(tm), "r"(bar), "r"(c0), "r"(c1) : "memory");
}
__device__ __forceinline__ void tma3d(uint32_t dst, const CUtensorMap* tm, uint32_t bar, int c0, int c1, int c2) {
  asm volatile("cp.async.bulk.tensor.3d.shared::cluster.global.mbarrier::complete_tx::bytes [%0], [%1, {%3, %4, %5}], [%2];"
               ::"r"(dst), "l"(tm), "r"(bar), "r"(c0), "r"(c1), "r"(c2) : "memory");
}
__device__ __forceinline__ void tma3d_mc(uint32_t dst, const CUtensorMap* tm, uint32_t bar, int c0, int c1, int c2) {
  asm volatile("cp.async.bulk.tensor.3d.shared::cluster.global.mbarrier::complete_tx::bytes.multicast::cluster [%0], [%1, {%3, %4, %5}], [%2], %6;"
               ::"r"(dst), "l"(tm), "r"(bar), "r"(c0), "r"(c1), "r"(c2), "h"((uint16_t)3) : "memory");
}
__device__ __forceinline__ void tma3d_prefetch(const CUtensorMap* tm, int c0, int c1, int c2) {
  asm volatile("cp.async.bulk.prefetch.tensor.3d.L2.global.tile [%0, {%1, %2, %3}];"
               ::"l"(tm), "r"(c0), "r"(c1), "r"(c2) : "memory");
}
__device__ __forceinline__ void tma2d_store(const CUtensorMap* tm, uint32_t src, int c0, int c1) {
  asm volatile("cp.async.bulk.tensor.2d.global.shared::cta.bulk_group [%0, {%2, %3}], [%1];"
               ::"l"(tm), "r"(src), "r"(c0), "r"(c1) : "memory");
}
__device__ __forceinline__ void tma3d_store(const CUtensorMap* tm, uint32_t src, int c0, int c1, int c2) {
  asm volatile("cp.async.bulk.tensor.3d.global.shared::cta.bulk_group [%0, {%2, %3, %4}], [%1];"
               ::"l"(tm), "r"(src), "r"(c0), "r"(c1), "r"(c2) : "memory");
}
__device__ __forceinline__ void bulk_g2s(uint32_t dst, const void* src, uint32_t bytes, uint32_t bar) {
  asm volatile("cp.async.bulk.shared::cluster.global.mbarrier::complete_tx::bytes [%0], [%1], %2, [%3];"
               ::"r"(dst), "l"(src), "r"(bytes), "r"(bar) : "memory");
}
__device__ __forceinline__ void bulk_s2g(void* dst, uint32_t src, uint32_t bytes) {
  asm volatile("cp.async.bulk.global.shared::cta.bulk_group [%0], [%1], %2;" ::"l"(dst), "r"(src), "r"(bytes) : "memory");
}
__device__ __forceinline__ void bulk_commit() { asm volatile("cp.async.bulk.commit_group;" ::: "memory"); }
__device__ __forceinline__ void bulk_wait0() { asm volatile("cp.async.bulk.wait_group 0;" ::: "memory"); }
__device__ __forceinline__ void l2_prefetch(const void* p, uint32_t bytes) {
  asm volatile("cp.async.bulk.prefetch.L2.global [%0], %1;" ::"l"(p), "r"(bytes) : "memory");
}
__device__ __forceinline__ void prefetch_tm(const CUtensorMap* tm) {
  asm volatile("prefetch.tensormap [%0];" ::"l"(tm) : "memory");
}
__device__ __forceinline__ uint64_t mkdesc(uint32_t addr, uint32_t lbo, uint32_t sbo, uint32_t sw) {
  return (uint64_t)((addr & 0x3FFFF) >> 4) | ((uint64_t)(lbo >> 4) << 16) | ((uint64_t)(sbo >> 4) << 32) | ((uint64_t)sw << 62);
}
__device__ __forceinline__ uint32_t dlo(uint32_t addr, uint32_t lbo) { return ((addr & 0x3FFFF) >> 4) | ((lbo >> 4) << 16); }
__device__ __forceinline__ uint64_t dsc(uint32_t lo, uint32_t off, uint32_t sbo, uint32_t sw) {
  return (uint64_t)(lo + (off >> 4)) | ((uint64_t)((sbo >> 4) | (sw << 30)) << 32);
}
__device__ __forceinline__ void wg_fence() { asm volatile("wgmma.fence.sync.aligned;" ::: "memory"); }
__device__ __forceinline__ void wg_commit() { asm volatile("wgmma.commit_group.sync.aligned;" ::: "memory"); }
template <int N> __device__ __forceinline__ void wg_wait() { asm volatile("wgmma.wait_group.sync.aligned %0;" ::"n"(N) : "memory"); }
template <int N> __device__ __forceinline__ void reg_fence(float (&d)[N]) {
#pragma unroll
  for (int i = 0; i < N; i++) asm volatile("" : "+f"(d[i])::"memory");
}
template <int N> __device__ __forceinline__ void reg_fence_u(uint32_t (&d)[N]) {
#pragma unroll
  for (int i = 0; i < N; i++) asm volatile("" : "+r"(d[i])::"memory");
}
__device__ __forceinline__ uint32_t pack_bf16(float lo, float hi) {
  uint32_t r;
  asm("cvt.rn.bf16x2.f32 %0, %1, %2;" : "=r"(r) : "f"(hi), "f"(lo));
  return r;
}
__device__ __forceinline__ uint32_t relu_sq_bf16(float lo, float hi) {
  uint32_t r;
  asm("{\n.reg .b32 t;\ncvt.rn.relu.bf16x2.f32 t, %1, %2;\nmul.rn.bf16x2 %0, t, t;\n}\n" : "=r"(r) : "f"(hi), "f"(lo));
  return r;
}
__device__ __forceinline__ float bf_lo(uint32_t v) { return __uint_as_float(v << 16); }
__device__ __forceinline__ float bf_hi(uint32_t v) { return __uint_as_float(v & 0xffff0000u); }
__device__ __forceinline__ uint32_t lds32(uint32_t a) { uint32_t v; asm volatile("ld.shared.u32 %0, [%1];" : "=r"(v) : "r"(a)); return v; }
__device__ __forceinline__ uint32_t lds16(uint32_t a) { uint16_t v; asm volatile("ld.shared.u16 %0, [%1];" : "=h"(v) : "r"(a)); return v; }
__device__ __forceinline__ float lds_f(uint32_t a) { float v; asm volatile("ld.shared.f32 %0, [%1];" : "=f"(v) : "r"(a)); return v; }
__device__ __forceinline__ uint2 lds64(uint32_t a) { uint2 v; asm volatile("ld.shared.v2.u32 {%0,%1}, [%2];" : "=r"(v.x), "=r"(v.y) : "r"(a)); return v; }
__device__ __forceinline__ uint4 lds128(uint32_t a) {
  uint4 v; asm volatile("ld.shared.v4.u32 {%0,%1,%2,%3}, [%4];" : "=r"(v.x), "=r"(v.y), "=r"(v.z), "=r"(v.w) : "r"(a)); return v;
}
__device__ __forceinline__ float4 lds128f(uint32_t a) {
  float4 v; asm volatile("ld.shared.v4.f32 {%0,%1,%2,%3}, [%4];" : "=f"(v.x), "=f"(v.y), "=f"(v.z), "=f"(v.w) : "r"(a)); return v;
}
__device__ __forceinline__ void sts16(uint32_t a, uint32_t v) { asm volatile("st.shared.u16 [%0], %1;" ::"r"(a), "h"((uint16_t)v) : "memory"); }
__device__ __forceinline__ void sts32(uint32_t a, uint32_t v) { asm volatile("st.shared.u32 [%0], %1;" ::"r"(a), "r"(v) : "memory"); }
__device__ __forceinline__ void sts_f(uint32_t a, float v) { asm volatile("st.shared.f32 [%0], %1;" ::"r"(a), "f"(v) : "memory"); }
__device__ __forceinline__ void sts128(uint32_t a, uint32_t x, uint32_t y, uint32_t z, uint32_t w) {
  asm volatile("st.shared.v4.u32 [%0], {%1,%2,%3,%4};" ::"r"(a), "r"(x), "r"(y), "r"(z), "r"(w) : "memory");
}
__device__ __forceinline__ void sts128p(uint32_t a, uint32_t x, uint32_t y, uint32_t z, uint32_t w, uint32_t p) {
  asm volatile("{\n.reg .pred q;\nsetp.ne.u32 q, %5, 0;\n@q st.shared.v4.u32 [%0], {%1,%2,%3,%4};\n}\n" ::"r"(a), "r"(x), "r"(y), "r"(z), "r"(w), "r"(p) : "memory");
}
__device__ __forceinline__ void sts128f(uint32_t a, float x, float y, float z, float w) {
  asm volatile("st.shared.v4.f32 [%0], {%1,%2,%3,%4};" ::"r"(a), "f"(x), "f"(y), "f"(z), "f"(w) : "memory");
}
__device__ __forceinline__ void stmatrix4(uint32_t a, uint32_t r0, uint32_t r1, uint32_t r2, uint32_t r3) {
  asm volatile("stmatrix.sync.aligned.m8n8.x4.shared.b16 [%0], {%1,%2,%3,%4};" ::"r"(a), "r"(r0), "r"(r1), "r"(r2), "r"(r3) : "memory");
}
__device__ __forceinline__ void stmatrix4t(uint32_t a, uint32_t r0, uint32_t r1, uint32_t r2, uint32_t r3) {
  asm volatile("stmatrix.sync.aligned.m8n8.x4.trans.shared.b16 [%0], {%1,%2,%3,%4};" ::"r"(a), "r"(r0), "r"(r1), "r"(r2), "r"(r3) : "memory");
}
__device__ __forceinline__ void ldmatrix4(uint32_t a, uint32_t& r0, uint32_t& r1, uint32_t& r2, uint32_t& r3) {
  asm volatile("ldmatrix.sync.aligned.m8n8.x4.shared.b16 {%0,%1,%2,%3}, [%4];" : "=r"(r0), "=r"(r1), "=r"(r2), "=r"(r3) : "r"(a) : "memory");
}
__device__ __forceinline__ void ldmatrix4t(uint32_t a, uint32_t& r0, uint32_t& r1, uint32_t& r2, uint32_t& r3) {
  asm volatile("ldmatrix.sync.aligned.m8n8.x4.trans.shared.b16 {%0,%1,%2,%3}, [%4];" : "=r"(r0), "=r"(r1), "=r"(r2), "=r"(r3) : "r"(a) : "memory");
}
__device__ __forceinline__ uint4 ldg128(const void* p) {
  uint4 v; asm volatile("ld.global.nc.v4.u32 {%0,%1,%2,%3}, [%4];" : "=r"(v.x), "=r"(v.y), "=r"(v.z), "=r"(v.w) : "l"(p)); return v;
}
__device__ __forceinline__ uint32_t ldg32(const void* p) {
  uint32_t v; asm volatile("ld.global.nc.u32 %0, [%1];" : "=r"(v) : "l"(p)); return v;
}
__device__ __forceinline__ uint4 ld_relaxed128(const void* p) {
  uint4 v; asm volatile("ld.relaxed.gpu.global.v4.u32 {%0,%1,%2,%3}, [%4];" : "=r"(v.x), "=r"(v.y), "=r"(v.z), "=r"(v.w) : "l"(p) : "memory"); return v;
}
__device__ __forceinline__ void st_relaxed128(void* p, uint32_t x, uint32_t y, uint32_t z, uint32_t w) {
  asm volatile("st.relaxed.gpu.global.v4.u32 [%0], {%1,%2,%3,%4};" ::"l"(p), "r"(x), "r"(y), "r"(z), "r"(w) : "memory");
}
__device__ __forceinline__ float ldbf(const __nv_bfloat16* p) { return __bfloat162float(__ldg(p)); }

__device__ __forceinline__ void wg_ss_n192(float (&d)[96], uint64_t da, uint64_t db, int scale_d){
  asm volatile("{\n.reg .pred p;\nsetp.ne.b32 p, %98, 0;\n"
    "wgmma.mma_async.sync.aligned.m64n192k16.f32.bf16.bf16 {%0, %1, %2, %3, %4, %5, %6, %7, %8, %9, %10, %11, %12, %13, %14, %15, %16, %17, %18, %19, %20, %21, %22, %23, %24, %25, %26, %27, %28, %29, %30, %31, %32, %33, %34, %35, %36, %37, %38, %39, %40, %41, %42, %43, %44, %45, %46, %47, %48, %49, %50, %51, %52, %53, %54, %55, %56, %57, %58, %59, %60, %61, %62, %63, %64, %65, %66, %67, %68, %69, %70, %71, %72, %73, %74, %75, %76, %77, %78, %79, %80, %81, %82, %83, %84, %85, %86, %87, %88, %89, %90, %91, %92, %93, %94, %95}, %96, %97, p, 1, 1, 0, 1;\n}\n"
    : "+f"(d[0]), "+f"(d[1]), "+f"(d[2]), "+f"(d[3]), "+f"(d[4]), "+f"(d[5]), "+f"(d[6]), "+f"(d[7]), "+f"(d[8]), "+f"(d[9]), "+f"(d[10]), "+f"(d[11]), "+f"(d[12]), "+f"(d[13]), "+f"(d[14]), "+f"(d[15]), "+f"(d[16]), "+f"(d[17]), "+f"(d[18]), "+f"(d[19]), "+f"(d[20]), "+f"(d[21]), "+f"(d[22]), "+f"(d[23]), "+f"(d[24]), "+f"(d[25]), "+f"(d[26]), "+f"(d[27]), "+f"(d[28]), "+f"(d[29]), "+f"(d[30]), "+f"(d[31]), "+f"(d[32]), "+f"(d[33]), "+f"(d[34]), "+f"(d[35]), "+f"(d[36]), "+f"(d[37]), "+f"(d[38]), "+f"(d[39]), "+f"(d[40]), "+f"(d[41]), "+f"(d[42]), "+f"(d[43]), "+f"(d[44]), "+f"(d[45]), "+f"(d[46]), "+f"(d[47]), "+f"(d[48]), "+f"(d[49]), "+f"(d[50]), "+f"(d[51]), "+f"(d[52]), "+f"(d[53]), "+f"(d[54]), "+f"(d[55]), "+f"(d[56]), "+f"(d[57]), "+f"(d[58]), "+f"(d[59]), "+f"(d[60]), "+f"(d[61]), "+f"(d[62]), "+f"(d[63]), "+f"(d[64]), "+f"(d[65]), "+f"(d[66]), "+f"(d[67]), "+f"(d[68]), "+f"(d[69]), "+f"(d[70]), "+f"(d[71]), "+f"(d[72]), "+f"(d[73]), "+f"(d[74]), "+f"(d[75]), "+f"(d[76]), "+f"(d[77]), "+f"(d[78]), "+f"(d[79]), "+f"(d[80]), "+f"(d[81]), "+f"(d[82]), "+f"(d[83]), "+f"(d[84]), "+f"(d[85]), "+f"(d[86]), "+f"(d[87]), "+f"(d[88]), "+f"(d[89]), "+f"(d[90]), "+f"(d[91]), "+f"(d[92]), "+f"(d[93]), "+f"(d[94]), "+f"(d[95])
    : "l"(da), "l"(db), "r"(scale_d));
}
__device__ __forceinline__ void wg_ss_n160(float (&d)[80], uint64_t da, uint64_t db, int scale_d){
  asm volatile("{\n.reg .pred p;\nsetp.ne.b32 p, %82, 0;\n"
    "wgmma.mma_async.sync.aligned.m64n160k16.f32.bf16.bf16 {%0, %1, %2, %3, %4, %5, %6, %7, %8, %9, %10, %11, %12, %13, %14, %15, %16, %17, %18, %19, %20, %21, %22, %23, %24, %25, %26, %27, %28, %29, %30, %31, %32, %33, %34, %35, %36, %37, %38, %39, %40, %41, %42, %43, %44, %45, %46, %47, %48, %49, %50, %51, %52, %53, %54, %55, %56, %57, %58, %59, %60, %61, %62, %63, %64, %65, %66, %67, %68, %69, %70, %71, %72, %73, %74, %75, %76, %77, %78, %79}, %80, %81, p, 1, 1, 0, 1;\n}\n"
    : "+f"(d[0]), "+f"(d[1]), "+f"(d[2]), "+f"(d[3]), "+f"(d[4]), "+f"(d[5]), "+f"(d[6]), "+f"(d[7]), "+f"(d[8]), "+f"(d[9]), "+f"(d[10]), "+f"(d[11]), "+f"(d[12]), "+f"(d[13]), "+f"(d[14]), "+f"(d[15]), "+f"(d[16]), "+f"(d[17]), "+f"(d[18]), "+f"(d[19]), "+f"(d[20]), "+f"(d[21]), "+f"(d[22]), "+f"(d[23]), "+f"(d[24]), "+f"(d[25]), "+f"(d[26]), "+f"(d[27]), "+f"(d[28]), "+f"(d[29]), "+f"(d[30]), "+f"(d[31]), "+f"(d[32]), "+f"(d[33]), "+f"(d[34]), "+f"(d[35]), "+f"(d[36]), "+f"(d[37]), "+f"(d[38]), "+f"(d[39]), "+f"(d[40]), "+f"(d[41]), "+f"(d[42]), "+f"(d[43]), "+f"(d[44]), "+f"(d[45]), "+f"(d[46]), "+f"(d[47]), "+f"(d[48]), "+f"(d[49]), "+f"(d[50]), "+f"(d[51]), "+f"(d[52]), "+f"(d[53]), "+f"(d[54]), "+f"(d[55]), "+f"(d[56]), "+f"(d[57]), "+f"(d[58]), "+f"(d[59]), "+f"(d[60]), "+f"(d[61]), "+f"(d[62]), "+f"(d[63]), "+f"(d[64]), "+f"(d[65]), "+f"(d[66]), "+f"(d[67]), "+f"(d[68]), "+f"(d[69]), "+f"(d[70]), "+f"(d[71]), "+f"(d[72]), "+f"(d[73]), "+f"(d[74]), "+f"(d[75]), "+f"(d[76]), "+f"(d[77]), "+f"(d[78]), "+f"(d[79])
    : "l"(da), "l"(db), "r"(scale_d));
}
__device__ __forceinline__ void wg_ss_n8(float (&d)[4], uint64_t da, uint64_t db, int scale_d){
  asm volatile("{\n.reg .pred p;\nsetp.ne.b32 p, %6, 0;\n"
    "wgmma.mma_async.sync.aligned.m64n8k16.f32.bf16.bf16 {%0, %1, %2, %3}, %4, %5, p, 1, 1, 0, 0;\n}\n"
    : "+f"(d[0]), "+f"(d[1]), "+f"(d[2]), "+f"(d[3])
    : "l"(da), "l"(db), "r"(scale_d));
}
__device__ __forceinline__ void wg_ss_n64_k(float (&d)[32], uint64_t da, uint64_t db, int scale_d){
  asm volatile("{\n.reg .pred p;\nsetp.ne.b32 p, %34, 0;\n"
    "wgmma.mma_async.sync.aligned.m64n64k16.f32.bf16.bf16 {%0, %1, %2, %3, %4, %5, %6, %7, %8, %9, %10, %11, %12, %13, %14, %15, %16, %17, %18, %19, %20, %21, %22, %23, %24, %25, %26, %27, %28, %29, %30, %31}, %32, %33, p, 1, 1, 0, 0;\n}\n"
    : "+f"(d[0]), "+f"(d[1]), "+f"(d[2]), "+f"(d[3]), "+f"(d[4]), "+f"(d[5]), "+f"(d[6]), "+f"(d[7]), "+f"(d[8]), "+f"(d[9]), "+f"(d[10]), "+f"(d[11]), "+f"(d[12]), "+f"(d[13]), "+f"(d[14]), "+f"(d[15]), "+f"(d[16]), "+f"(d[17]), "+f"(d[18]), "+f"(d[19]), "+f"(d[20]), "+f"(d[21]), "+f"(d[22]), "+f"(d[23]), "+f"(d[24]), "+f"(d[25]), "+f"(d[26]), "+f"(d[27]), "+f"(d[28]), "+f"(d[29]), "+f"(d[30]), "+f"(d[31])
    : "l"(da), "l"(db), "r"(scale_d));
}
__device__ __forceinline__ void wg_ss_n48_t(float (&d)[24], uint64_t da, uint64_t db, int scale_d){
  asm volatile("{\n.reg .pred p;\nsetp.ne.b32 p, %26, 0;\n"
    "wgmma.mma_async.sync.aligned.m64n48k16.f32.bf16.bf16 {%0, %1, %2, %3, %4, %5, %6, %7, %8, %9, %10, %11, %12, %13, %14, %15, %16, %17, %18, %19, %20, %21, %22, %23}, %24, %25, p, 1, 1, 0, 1;\n}\n"
    : "+f"(d[0]), "+f"(d[1]), "+f"(d[2]), "+f"(d[3]), "+f"(d[4]), "+f"(d[5]), "+f"(d[6]), "+f"(d[7]), "+f"(d[8]), "+f"(d[9]), "+f"(d[10]), "+f"(d[11]), "+f"(d[12]), "+f"(d[13]), "+f"(d[14]), "+f"(d[15]), "+f"(d[16]), "+f"(d[17]), "+f"(d[18]), "+f"(d[19]), "+f"(d[20]), "+f"(d[21]), "+f"(d[22]), "+f"(d[23])
    : "l"(da), "l"(db), "r"(scale_d));
}
__device__ __forceinline__ void wg_ss_n32_t(float (&d)[16], uint64_t da, uint64_t db, int scale_d){
  asm volatile("{\n.reg .pred p;\nsetp.ne.b32 p, %18, 0;\n"
    "wgmma.mma_async.sync.aligned.m64n32k16.f32.bf16.bf16 {%0, %1, %2, %3, %4, %5, %6, %7, %8, %9, %10, %11, %12, %13, %14, %15}, %16, %17, p, 1, 1, 0, 1;\n}\n"
    : "+f"(d[0]), "+f"(d[1]), "+f"(d[2]), "+f"(d[3]), "+f"(d[4]), "+f"(d[5]), "+f"(d[6]), "+f"(d[7]), "+f"(d[8]), "+f"(d[9]), "+f"(d[10]), "+f"(d[11]), "+f"(d[12]), "+f"(d[13]), "+f"(d[14]), "+f"(d[15])
    : "l"(da), "l"(db), "r"(scale_d));
}
__device__ __forceinline__ void wg_kgen(float (&d)[24], uint64_t da, uint64_t db, int scale_d){
  asm volatile("{\n.reg .pred p;\nsetp.ne.b32 p, %26, 0;\n"
    "wgmma.mma_async.sync.aligned.m64n48k16.f32.f16.f16 {%0, %1, %2, %3, %4, %5, %6, %7, %8, %9, %10, %11, %12, %13, %14, %15, %16, %17, %18, %19, %20, %21, %22, %23}, %24, %25, p, 1, 1, 1, 1;\n}\n"
    : "+f"(d[0]), "+f"(d[1]), "+f"(d[2]), "+f"(d[3]), "+f"(d[4]), "+f"(d[5]), "+f"(d[6]), "+f"(d[7]), "+f"(d[8]), "+f"(d[9]), "+f"(d[10]), "+f"(d[11]), "+f"(d[12]), "+f"(d[13]), "+f"(d[14]), "+f"(d[15]), "+f"(d[16]), "+f"(d[17]), "+f"(d[18]), "+f"(d[19]), "+f"(d[20]), "+f"(d[21]), "+f"(d[22]), "+f"(d[23])
    : "l"(da), "l"(db), "r"(scale_d));
}
__device__ __forceinline__ void wg_rs_n64_k(float (&d)[32], uint32_t a0, uint32_t a1, uint32_t a2, uint32_t a3, uint64_t db, int scale_d){
  asm volatile("{\n.reg .pred p;\nsetp.ne.b32 p, %37, 0;\n"
    "wgmma.mma_async.sync.aligned.m64n64k16.f32.bf16.bf16 {%0, %1, %2, %3, %4, %5, %6, %7, %8, %9, %10, %11, %12, %13, %14, %15, %16, %17, %18, %19, %20, %21, %22, %23, %24, %25, %26, %27, %28, %29, %30, %31}, {%32,%33,%34,%35}, %36, p, 1, 1, 0;\n}\n"
    : "+f"(d[0]), "+f"(d[1]), "+f"(d[2]), "+f"(d[3]), "+f"(d[4]), "+f"(d[5]), "+f"(d[6]), "+f"(d[7]), "+f"(d[8]), "+f"(d[9]), "+f"(d[10]), "+f"(d[11]), "+f"(d[12]), "+f"(d[13]), "+f"(d[14]), "+f"(d[15]), "+f"(d[16]), "+f"(d[17]), "+f"(d[18]), "+f"(d[19]), "+f"(d[20]), "+f"(d[21]), "+f"(d[22]), "+f"(d[23]), "+f"(d[24]), "+f"(d[25]), "+f"(d[26]), "+f"(d[27]), "+f"(d[28]), "+f"(d[29]), "+f"(d[30]), "+f"(d[31])
    : "r"(a0), "r"(a1), "r"(a2), "r"(a3), "l"(db), "r"(scale_d));
}

struct cf { float r, i; };
__device__ __forceinline__ cf cmul(cf a, cf b) { return cf{fmaf(a.r, b.r, -a.i * b.i), fmaf(a.r, b.i, a.i * b.r)}; }
__device__ __forceinline__ cf csqr(cf a) { return cf{fmaf(a.r, a.r, -a.i * a.i), (a.r + a.r) * a.i}; }
__device__ __forceinline__ cf zpow(float a2, float th, float tl, float p) {
  float mag;
  asm("ex2.approx.ftz.f32 %0, %1;" : "=f"(mag) : "f"(a2 * p));
  const float x = th * p;
  const float ang = ((x - rintf(x)) + tl * p) * 6.283185307179586f;
  return cf{mag * __cosf(ang), mag * __sinf(ang)};
}
struct ch2 { __half2 r, i; };
__device__ __forceinline__ ch2 hpack(cf a, cf b) { return ch2{__floats2half2_rn(a.r, b.r), __floats2half2_rn(a.i, b.i)}; }
__device__ __forceinline__ ch2 hpackc(cf a, cf b) { return ch2{__floats2half2_rn(a.r, b.r), __floats2half2_rn(-a.i, -b.i)}; }
__device__ __forceinline__ ch2 hmul(ch2 a, ch2 m) {
  return ch2{__hfma2(a.r, m.r, __hneg2(__hmul2(a.i, m.i))), __hfma2(a.r, m.i, __hmul2(a.i, m.r))};
}
__device__ __forceinline__ uint32_t h2u(__half2 v) { return *reinterpret_cast<uint32_t*>(&v); }
__device__ __forceinline__ void hst(uint32_t a, uint32_t d, ch2 v0, ch2 v1, ch2 v2, ch2 v3) {
  sts128(a, h2u(v0.r), h2u(v1.r), h2u(v2.r), h2u(v3.r));
  sts128(a + d, h2u(v0.i), h2u(v1.i), h2u(v2.i), h2u(v3.i));
}
__device__ __forceinline__ uint32_t ldg16(const void* p) {
  uint16_t v; asm volatile("ld.global.nc.u16 %0, [%1];" : "=h"(v) : "l"(p)); return v;
}
struct KZ { cf z1, z2, z4, z8, z16, z32, z64, z128, z136, z256, z512; };
__device__ __forceinline__ KZ kgen_pre(const uint32_t (&p)[7]) {
  const float dt = __bfloat162float(__float2bfloat16(expf(bf_lo(p[6]))));
  const float a2 = (dt * bf_lo(p[0])) * 1.4426950408889634f;
  const float bb = dt * bf_lo(p[1]);
  const float th = bb * 0.15915494309189535f;
  const float tl = fmaf(bb, 0.15915494309189535f, -th);
  KZ k;
  k.z1 = zpow(a2, th, tl, 1.f); k.z64 = zpow(a2, th, tl, 64.f);
  k.z2 = csqr(k.z1); k.z128 = csqr(k.z64); k.z4 = csqr(k.z2); k.z256 = csqr(k.z128); k.z8 = csqr(k.z4); k.z512 = csqr(k.z256);
  k.z16 = csqr(k.z8); k.z136 = cmul(k.z128, k.z8); k.z32 = csqr(k.z16);
  asm volatile("" : "+f"(k.z32.r), "+f"(k.z32.i), "+f"(k.z136.r), "+f"(k.z136.i), "+f"(k.z512.r), "+f"(k.z512.i)::"memory");
  return k;
}
__device__ __forceinline__ void kgen_rows(const KZ& k, uint32_t ua) {
  const ch2 m16 = hpackc(k.z16, k.z16), m32 = hpackc(k.z32, k.z32), m64 = hpackc(k.z64, k.z64);
#pragma unroll
  for (int h = 0; h < 2; h++) {
    const ch2 a0 = h ? hpackc(k.z128, k.z136) : hpackc(cf{1.f, 0.f}, k.z8);
    const ch2 a1 = hmul(a0, m16), a2_ = hmul(a0, m32), a3 = hmul(a1, m32);
    hst(ua + 512 * h, 2048, a0, a1, a2_, a3);
    hst(ua + 512 * h + 256, 2048, hmul(a0, m64), hmul(a1, m64), hmul(a2_, m64), hmul(a3, m64));
  }
}
__device__ __forceinline__ void kgen_cols(const KZ& k, const uint32_t (&p)[7], float sB, float sC, uint32_t ub) {
  const cf W = cmul(cf{bf_lo(p[4]) * sC, bf_lo(p[5]) * sC}, cf{bf_lo(p[2]) * sB, bf_lo(p[3]) * sB});
  const ch2 m2 = hpack(k.z2, k.z2), m4 = hpack(k.z4, k.z4), m256 = hpack(k.z256, k.z256), m512 = hpack(k.z512, k.z512);
  const ch2 p0 = hpack(W, cmul(W, k.z1)), p2 = hmul(p0, m2);
  hst(ub, 1536, p0, p2, hmul(p0, m4), hmul(p2, m4));
  const cf W256 = cmul(W, k.z256), W260 = cmul(W256, k.z4), W516 = cmul(W260, k.z256), W520 = cmul(W516, k.z4);
  const cf W1032 = cmul(W520, k.z512);
  const ch2 q0 = hpack(cmul(W256, k.z2), W260), q2 = hpack(W516, W520);
  hst(ub + 256, 1536, q0, hmul(q0, m4), q2, hmul(q2, m256));
  const ch2 r0 = hpack(W1032, cmul(W1032, k.z256));
  const __half2 zz = __floats2half2_rn(0.f, 0.f);
  hst(ub + 512, 1536, r0, hmul(r0, m512), hpack(W256, cf{0.f, 0.f}), ch2{zz, zz});
}
__device__ __forceinline__ void kgen_scatter(const float (&v)[12], uint32_t kc, int q0, int t4, float fs, float dsk) {
#pragma unroll
  for (int h = 0; h < 2; h++) {
    const int q = q0 + 8 * h;
    const float x0 = v[2 * h] * fs + ((q | t4) == 0 ? dsk : 0.f);
    sts32(kc + 2 * (262 - 8 * q - 2 * t4), pack_bf16(v[2 * h + 1] * fs, x0));
    const uint32_t s1 = pack_bf16(v[4 + 2 * h + 1] * fs, v[4 + 2 * h] * fs), s2 = pack_bf16(v[8 + 2 * h] * fs, v[8 + 2 * h + 1] * fs);
    if (t4 < 2) {
      const uint32_t a = kc + 2 * (530 - 4 * t4 - 8 * q);
      sts32(a, __byte_perm(s1, 0, 0x1010)); sts32(a + 4, s1);
      if (q == 31 && t4 == 1) sts16(kc + 2 * 277, s1);
      const uint32_t a3 = kc + 2 * (767 + 72 * ((q & 1) ^ 1) - 32 * t4 - (q >> 1));
      sts16(a3, s2); sts16(a3 - 32, s2 >> 16);
    } else {
      const uint32_t a = kc + 2 * (575 + 40 * (t4 - 2) - q);
      sts16(a, s1); sts16(a + 160, s1 >> 16);
      if (q == 0 && t4 == 2) sts32(kc + 2 * 534, __byte_perm(s2, 0, 0x1010));
    }
  }
}
__device__ __forceinline__ void toeplitz(uint32_t src, uint32_t t, uint32_t p) {
  const uint4 x = lds128(src), y = lds128(src + 16);
  const uint32_t e[8] = {x.x, x.y, x.z, x.w, y.x, y.y, y.z, y.w};
  uint32_t o[7];
#pragma unroll
  for (int i = 0; i < 7; i++) o[i] = __byte_perm(e[i], e[i + 1], 0x5432);
#pragma unroll
  for (int i = 0; i < 4; i++) {
    sts128p(t + 16 * (7 - 2 * i), e[i], e[i + 1], e[i + 2], e[i + 3], p);
    sts128p(t + 16 * (6 - 2 * i), o[i], o[i + 1], o[i + 2], o[i + 3], p);
  }
}

__global__ void __cluster_dims__(2, 1, 1) __launch_bounds__(NTHREADS, 1)
fused_kernel(const __grid_constant__ CUtensorMap tm_x, const __grid_constant__ CUtensorMap tm_w1,
             const __grid_constant__ CUtensorMap tm_hld,
             const __grid_constant__ CUtensorMap tm_w2a, const __grid_constant__ CUtensorMap tm_w2b, const __grid_constant__ CUtensorMap tm_u,
             const __grid_constant__ CUtensorMap tm_aT, const __grid_constant__ CUtensorMap tm_out,
             const __grid_constant__ CUtensorMap tm_ust, const __grid_constant__ CUtensorMap tm_ast, const Params P) {
  extern __shared__ __align__(1024) uint8_t smem[];
  const uint32_t sb = __shfl_sync(0xffffffffu, smem_u32(smem), 0);
  const int tid = threadIdx.x, warp = __shfl_sync(0xffffffffu, tid >> 5, 0), lane = tid & 31;
  int pr = blockIdx.x >> 1;
  const int kh = blockIdx.x & 1;
  if (P.use_smid) {
    uint32_t smid;
    asm volatile("mov.u32 %0, %%smid;" : "=r"(smid));
    const int tpc = smid >> 1, q = tpc - 32;
    pr = tpc < 32 ? (tpc & 7) * 8 + (tpc >> 3) : tpc < 60 ? (1 + q % 7) * 8 + 4 + q / 7 : tpc < 62 ? tpc + 4 : tpc - 58;
  }
  if (pr < 64) pr = (pr & 48) | ((pr & 6) << 1) | ((pr >> 2) & 2) | (pr & 1);
  const int b = 2 * pr + kh, m = pr >> 2, nt = pr & 3, j = kh * 4 + nt;
  if (pr >= 64) {
    if (tid == 0) {
      const unsigned e = ld_relaxed(&g_epoch[b * 8]) + 1;
      for (int i = 0; i < 4; i++)
        for (uint32_t n = 0; n < (1u << 16) && !flag_try(&g_aflag[i * 32], 32u * e); n++) __nanosleep(200);
      g_epoch[b * 8] = e;
    }
    return;
  }
  const uint32_t bars = sb + OFF_BAR;
  TSINIT();
  TS(0);
  auto BAR = [&](int i) { return bars + 8u * i; };
  auto kcoord = [&](int kb) {
    const int sg = (kb * 11) >> 5;
    return (kh * 4 + (sg < 2 ? nt ^ sg : (nt & 2) ^ sg)) * 192 + (kb - 3 * sg) * 64;
  };

  const int hi = lane >> 4, hw = warp >= 14 ? warp - 10 : warp - 8;
  const bool kg = (warp & 14) != 12, ssm = (warp >> 2) == 2;
  uint4 x[2][4];
  float ldt[2], dsk[2];
#pragma unroll
  for (int i = 0; i < 2; i++) {
    if (i == 0 ? warp >= 12 : warp == 15) {
      const int c = b * 5 + (i ? 4 : warp - 12), o = c * 192 + 8 * (lane < 24 ? lane : 0);
      x[i][0] = ldg128(P.Bre + o); x[i][1] = ldg128(P.Bim + o); x[i][2] = ldg128(P.Cre + o); x[i][3] = ldg128(P.Cim + o);
      ldt[i] = bf_lo(ldg16(P.logdt + c)); dsk[i] = bf_lo(ldg16(P.Dskip + c));
    }
  }
  uint32_t pn[3][7];
#pragma unroll
  for (int r = 0; r < 3; r++) {
    if (r < 2 ? warp < 12 : kg && warp >= 8) {
      const int c = 5 * b + (r < 2 ? 2 * r + hi : 4);
      const int o = c * 192 + (lane & 15) + (r < 2 ? 16 * warp : 16 * hw + 96 * hi);
      pn[r][0] = ldg16(P.Are + o); pn[r][1] = ldg16(P.Aim + o); pn[r][6] = ldg16(P.logdt + c); pn[r][2] = ldg16(P.Bre + o);
      pn[r][3] = ldg16(P.Bim + o); pn[r][4] = ldg16(P.Cre + o); pn[r][5] = ldg16(P.Cim + o);
    }
  }

  if (warp >= 12 && lane == 0) {
    const int it = warp - 12;
    if (it < 3) {
      const uint32_t st = sb + it * STAGE_BYTES;
      mbar_init(BAR(B_FULL + it), 1);
      fence_async_smem();
      mbar_expect_tx(BAR(B_FULL + it), it == 0 ? 40960 + 1280 + 320 : 40960);
      tma2d(st, &tm_x, BAR(B_FULL + it), 64 * it, 128 * m);
      tma3d(st + 16384, &tm_w1, BAR(B_FULL + it), 0, 64 * it, 3 * j);
      if (it == 0) {
        bulk_g2s(sb + OFF_GW, P.gw, 1280, BAR(B_FULL));
        bulk_g2s(sb + OFF_B2, P.b2 + 160 * nt, 320, BAR(B_FULL));
      }
      TSP(3, 2 + it);
    } else {
      mbar_init(BAR(B_UTILE), 1);
      fence_async_smem();
      mbar_expect_tx(BAR(B_UTILE), 20480);
      tma2d(sb + OFF_X, &tm_u, BAR(B_UTILE), 40 * m, 256 * (b & 7));
      prefetch_tm(&tm_ust);

    }
  }
  __syncwarp();
  float v[12], v1[12];
  if (warp < 8) {
#pragma unroll
    for (int i = 0; i < 12; i++) {
      v[i] = __uint_as_float(ldg32(P.b1 + 192 * j + 8 * i + 2 * (lane & 3)));
      v1[i] = __uint_as_float(ldg32(P.b1 + 192 * j + 96 + 8 * i + 2 * (lane & 3)));
    }
  }
  if (warp < 12 && lane == 0) {
    mbar_init(BAR(4 + warp), (uint32_t)(BAR_T0 >> (4 * warp)) & 15u);
    if (warp < NBAR - 16) mbar_init(BAR(16 + warp), (uint32_t)(BAR_T1 >> (4 * warp)) & 15u);
    if (warp == B_RED - 16) mbar_expect_tx(BAR(B_RED), 40960);
    asm volatile("fence.mbarrier_init.release.cluster;" ::: "memory");
  }
  __syncwarp();
  const uint32_t work = sb + OFF_WORK;
  if (warp >= 12) {
#pragma unroll 1
    for (int c = warp - 12;; c = 4) {
      const uint32_t M = 0x7f807f80u;
      uint32_t e[2];
#pragma unroll
      for (int i = 0; i < 2; i++) {
        const uint4 p = x[0][2 * i], q = x[0][2 * i + 1];
        e[i] = __vmaxu2(__vmaxu2(__vmaxu2(p.x & M, p.y & M), __vmaxu2(p.z & M, p.w & M)), __vmaxu2(__vmaxu2(q.x & M, q.y & M), __vmaxu2(q.z & M, q.w & M)));
        e[i] = __reduce_max_sync(0xffffffffu, max(e[i] >> 16, e[i] & 0xffffu)) >> 7;
      }
      const uint32_t eb = min(max(e[0], 1u), 253u), ec = min(max(e[1], 13u), 254u);
      const float dt = __bfloat162float(__float2bfloat16(expf(ldt[0])));
      if (lane == 0)
        sts128f(sb + OFF_SC + 16 * c, __uint_as_float((254u - eb) << 23), __uint_as_float((266u - ec) << 23),
                dt * __uint_as_float(eb << 23) * __uint_as_float((ec - 12u) << 23), dsk[0]);
      if (c != 3) break;
#pragma unroll
      for (int i = 0; i < 4; i++) x[0][i] = x[1][i];
      ldt[0] = ldt[1]; dsk[0] = dsk[1];
    }
    bar_sync(0, NTHREADS);
    asm volatile("barrier.cluster.arrive.relaxed.aligned;" ::: "memory");
    if (warp >= 13) {
      TSW(0);
      mbar_wait(BAR(B_UTILE), 0);
      TSW(1);
      const int bb = lane >> 3, rr = lane & 7;
      const uint32_t src = sb + OFF_X + (8 * (rr >> 1) + 2 * bb + (rr & 1)) * 80, dst = sb + OFF_X + lane * 32 + ((lane & 4) << 2);
#pragma unroll 1
      for (int p = warp == 13 ? 0 : warp - 12; p <= warp - 12; p++) {
        uint32_t t[40];
#pragma unroll
        for (int i = 0; i < 10; i++) {
          const int cg = (i >> 1) + (rr >> 1);
          ldmatrix4t(src + p * 5120 + (i & 1) * 2560 + (cg > 4 ? cg - 5 : cg) * 16, t[4 * i], t[4 * i + 1], t[4 * i + 2], t[4 * i + 3]);
        }
        __syncwarp();
#pragma unroll
        for (int i = 0; i < 10; i++) {
          const int cg = (i >> 1) + (lane & 3);
          sts128((dst ^ ((i & 1) << 4)) + p * 5120 + (cg > 4 ? cg - 5 : cg) * 1024, t[4 * i], t[4 * i + 1], t[4 * i + 2], t[4 * i + 3]);
        }
        fence_async_smem();
        __syncwarp();
        if (lane == 0) { tma3d_store(&tm_ust, sb + OFF_X + p * 5120, 0, 160 * m, 4 * (b & 7) + p); bulk_commit(); }
      }
      TSW(2);
      if (lane == 0) asm volatile("cp.async.bulk.wait_group.read 0;" ::: "memory");
      __syncwarp();
      TSW(3);
      if (warp == 13) {
#pragma unroll
        for (int i = lane; i < 50; i += 32) {
          const int c = i / 10, z = i % 10;
          sts128(sb + OFF_KC + c * KC_CHB + 16 * (z < 3 ? (z == 0 ? 0 : 32 + z) : z < 8 ? 52 + 5 * z : 24 + 9 * z), 0u, 0u, 0u, 0u);
        }
      } else {
        sts128(work + W5 + WD1 + (warp - 14) * 3584 + 16 * lane, 0u, 0u, 0u, 0u);
      }
      fence_async_smem();
      __syncwarp();
      if (lane == 0) {
        mbar_arrive(BAR(B_TFREE));
        bulk_wait0();
        flag_add(&g_uflag[m * 32]);
      }
      __syncwarp();
      TSW(4);
    }
  }

  float d[24];
#pragma unroll
  for (int i = 0; i < 24; i++) d[i] = 0.f;
  auto scatter = [&](int c) {
    const int w = warp & 3;
    c += w >> 1;
    const uint2 s = lds64(sb + OFF_SC + 16 * c + 8);
    kgen_scatter(v, sb + OFF_KC + c * KC_CHB, 16 * (w & 1) + (lane >> 2), lane & 3, __uint_as_float(s.x), __uint_as_float(s.y));
  };
  if (kg) {
    const uint32_t dka = dlo(work, 128), dkb = dlo(work + 4096, 128);
    const int r1 = warp < 8 ? 2 : ssm ? 4 : 3;
    if (warp >= 14) {
#pragma unroll
      for (int i = 0; i < 7; i++) pn[0][i] = pn[2][i];
    }
    reg_fence(d);
#pragma unroll 1
    for (int r = warp >= 14 ? 2 : 0; r < r1; r++) {
      uint32_t pc[7];
#pragma unroll
      for (int i = 0; i < 7; i++) { pc[i] = pn[0][i]; pn[0][i] = pn[1][i]; pn[1][i] = pn[2][i]; }
      KZ z;
      if (r < 3) {
        z = kgen_pre(pc);
        wg_wait<0>();
        reg_fence(d);
        if (r > 0 && ssm && lane == 0) mbar_arrive(BAR(B_KE + r - 1));
      }
      if (ssm && r >= 2) {
        mbar_wait(BAR(B_TFREE), 0);
        scatter(2 * r - 4);
        if (r == 3) break;
      }
      wg_wait<0>();
      reg_fence(d);
      if (r > 0) mbar_wait(BAR(B_KE + r - 1), 0);
      if (ssm) TS(2 + 3 * r);
      TSH(2 + 3 * r);
      const uint32_t ua = work + (r < 2 ? warp : hw) * SLOT + hi * 1024 + (lane & 15) * 16;
      kgen_rows(z, ua);
      if (r == 0) {
        bar_sync(0, NTHREADS);
        asm volatile("barrier.cluster.arrive.relaxed.aligned;" ::: "memory");
        TS(1);
      }
      const uint2 sc = lds64(sb + OFF_SC + 16 * (r < 2 ? 2 * r + hi : 4));
      kgen_cols(z, pc, __uint_as_float(sc.x), __uint_as_float(sc.y), ua + 4096 - hi * 256);
      fence_async_smem();
      __syncwarp();
      if (lane == 0) mbar_arrive(BAR(B_KF + r));
      TSH(3 + 3 * r);
      if (ssm) {
        TS(3 + 3 * r);
#pragma unroll
        for (int i = 0; i < 12; i++) v[i] = (warp & 2) ? d[12 + i] : d[i];
        mbar_wait(BAR(B_KF + r), 0);
        wg_fence();
#pragma unroll
        for (int k = 0; k < 12; k++)
          wg_kgen(d, dsc(dka, (k >> 1) * SLOT + (k & 1) * 2048, 256, 0), dsc(dkb, (k >> 1) * SLOT + (k & 1) * 1536, 256, 0), k != 0);
        wg_commit();
        if (r < 2) {
          wg_fence();
#pragma unroll
          for (int k = 12; k < 24; k++)
            wg_kgen(d, dsc(dka, (k >> 1) * SLOT + (k & 1) * 2048, 256, 0), dsc(dkb, (k >> 1) * SLOT + (k & 1) * 1536, 256, 0), 1);
          wg_commit();
        }
        TS(4 + 3 * r);
      }
    }
    wg_wait<0>();
    reg_fence(d);
  }
  auto table = [&](int k, uint32_t kc, uint32_t b01, uint32_t p) {
    int tsrc, tdst;
    if (k < 67) { const int e = k >> 1; tsrc = (k & 1) ? e : 33 + e; tdst = 4 * 288 + 144 + 144 * k + b01; }
    else if (k < 87) { const int q = k - 67, cl = q / 10, e = (q % 10) >> 1; tsrc = 67 + 10 * cl + 5 * (q & 1) + e; tdst = TA2 + cl * 3168 + 3 * 288 + 144 * (q % 10); }
    else { const int q = k - 87, cl = q / 11, x = q % 11;
      const int gr = x < 8 ? (x & 1) : 1, dd = x < 8 ? 3 - (x >> 1) : 7 - x;
      tsrc = 88 + 9 * cl + 7 - dd - 4 * gr; tdst = TA3 + cl * 2016 + (3 - dd) * 288 + 144 * gr; }
    toeplitz(kc + 16 * tsrc, work + tdst, p);
  };

  if (warp >= 12) {

    const unsigned epoch1 = ld_relaxed(&g_epoch[b * 8]) + 1;
    if (warp == 12 && lane == 0) l2_prefetch(P.w1 + (size_t)b * (FF * DM / NCTA), FF * DM / NCTA * 2);
    if (warp != 13) {
      const int ht = tid & 63;
      const uint32_t live = warp != 12;
      if (live) mbar_wait(BAR(B_UFULL), 0);
      TSH(14);
#pragma unroll 1
      for (int c = live ^ 1u; c < 6; c++) {
        const uint32_t uc = sb + OFF_UC + c * UC_CHB, kc = sb + OFF_KC + c * KC_CHB;
        const uint32_t wa = work + ((c & 1) ? 0 : WD1), wb = work + ((c & 1) ? 0 : WD2);
        uint32_t qq[3][10];
        if (c < 5) {
#pragma unroll
          for (int i = 0; i < 3; i++) {
            const int cc = ht + 38;
            const uint2 q0 = lds64(uc + (cc & 3) * UC_C + (cc >> 2) * 16 + 8 + 256 * i);
            const uint4 q1 = lds128(uc + ((cc + 1) & 3) * UC_C + ((cc + 1) >> 2) * 16 + 256 * i);
            const uint4 q2 = lds128(uc + ((cc + 2) & 3) * UC_C + ((cc + 2) >> 2) * 16 + 256 * i);
            qq[i][0] = q0.x; qq[i][1] = q0.y; qq[i][2] = q1.x; qq[i][3] = q1.y; qq[i][4] = q1.z; qq[i][5] = q1.w;
            qq[i][6] = q2.x; qq[i][7] = q2.y; qq[i][8] = q2.z;
          }
        }
        if (c > 0) {
          if (live) mbar_wait(BAR(B_WE), (c - 1) & 1);
          const uint32_t b01 = (c & 1) ? 0 : TA01A;
          if (ht < 45 && (ht < 42 || c < 5)) table(ht < 42 ? 67 + ht : 22 + ht, ht < 42 ? kc - KC_CHB : kc, b01, live);
          fence_async_smem();
          __syncwarp();
          if (lane == 0 && live) mbar_arrive(BAR(B_WF + 1));
          TSH(20 + c);
          if (c == 5) break;
          table(ht, kc, b01, live);
          if (c == 1) sts128p(work + W5 + (ht >> 5) * 3584 + 16 * lane, 0u, 0u, 0u, 0u, live);
        }
        if (ht == 0) sts128p(wb + W9, 0u, 0u, 0u, 0u, live);
#pragma unroll
        for (int i = 0; i < 3; i++) {
          const int ci = ht + 64 * i;
          float S[18];
          S[0] = 0.f;
#pragma unroll
          for (int e = 0; e < 17; e++) S[e + 1] = S[e] + ((e & 1) ? bf_hi(qq[i][e >> 1]) : bf_lo(qq[i][e >> 1]));
          auto win = [&](uint32_t a, int lo, int hi_) {
            uint32_t o[4];
#pragma unroll
            for (int e = 0; e < 4; e++)
              o[e] = pack_bf16(S[13 - hi_ + 2 * e] - S[12 - lo + 2 * e], S[14 - hi_ + 2 * e] - S[13 - lo + 2 * e]);
            sts128p(a, o[0], o[1], o[2], o[3], live);
          };
          win(wa + W5 + 512 + ci * 16, 10, 6);
          win(wa + W3 + 512 + ci * 16, 5, 3);
          if (i < 2) {
            const uint32_t off = wb + (ci & 1) * 1024 + (ci >> 1) * 16;
            win(off + W7, 11, 5);
            win(off + WC, 4, 3);
            if (ci < 127) win(wb + W9 + ((ci + 1) & 1) * 1024 + ((ci + 1) >> 1) * 16, 12, 4);
          }
        }
        if (c > 0) {
          fence_async_smem();
          __syncwarp();
          if (!live) break;
          if (lane == 0) mbar_arrive(BAR((c & 1) ? B_WF : B_WG));
        }
        TSH(15 + c);
      }
      TSHDUMP();

    }
    if (warp == 12) {
      TSV(10);
      int slot = 0, ph = 0;
#pragma unroll 1
      for (int n = 3; n < 22; n++) {
        const uint32_t st = sb + slot * STAGE_BYTES, fb = BAR(B_FULL + slot);
        const bool g1 = n < 10;
        const int kk = g1 ? 64 * n : kcoord(n - 10);
        mbar_wait(fb, ph);
        asm volatile("{\n.reg .pred p;\nelect.sync _|p, 0xffffffff;\n"
                     "@p mbarrier.arrive.expect_tx.shared::cta.b64 _, [%1], %10;\n"
                     "bar.sync %0, 288;\n"
                     "@p cp.async.bulk.tensor.3d.shared::cluster.global.mbarrier::complete_tx::bytes [%2], [%3, {0, %4, %5}], [%1];\n"
                     "@p cp.async.bulk.tensor.2d.shared::cluster.global.mbarrier::complete_tx::bytes [%6], [%7, {%8, %9}], [%1];\n}\n"
                     ::"r"(8 + slot), "r"(fb), "r"(st + 16384), "l"(g1 ? &tm_w1 : &tm_w2a), "r"(kk), "r"(g1 ? 3 * j : (5 * nt + 1) >> 1),
                       "r"(g1 ? st : st + 32768), "l"(g1 ? &tm_x : &tm_w2b), "r"(g1 ? kk : 160 * nt + ((nt & 1) ? 0 : 128)), "r"(g1 ? 128 * m : kk),
                       "r"(n >= 10 && n < 13 ? 24576 : 40960) : "memory");
        if (n == 5 && lane == 0) l2_prefetch(P.w2 + (size_t)b * (FF * DM / NCTA), FF * DM / NCTA * 2);
        if (++slot == 3) { slot = 0; ph ^= 1; }
      }
      if (lane == 0) {
        mbar_wait(BAR(B_SSMDONE), 0);
        flag_wait(&g_aflag[nt * 32], 32u * epoch1);
        mbar_expect_tx(BAR(B_AT), 20480);
        tma2d(sb + OFF_AT, &tm_aT, BAR(B_AT), 128 * m + 64 * kh, 160 * nt);
        g_epoch[b * 8] = epoch1;
        TSPDUMP();
      }
    } else if (warp == 13) {
      if (lane == 0) {
        prefetch_tm(&tm_w2a); prefetch_tm(&tm_w2b); prefetch_tm(&tm_hld); prefetch_tm(&tm_ast); prefetch_tm(&tm_aT); prefetch_tm(&tm_out);
        mbar_expect_tx(BAR(B_UFULL), 5 * UC_CHB);
        flag_wait(&g_uflag[m * 32], 24u * epoch1);
        TSW(5);
      }
      __syncwarp();
      mbar_wait(BAR(B_KE + 1), 0);
      if (lane == 0) bulk_g2s(sb + OFF_UC, g_uT + (size_t)b * 5 * UC_CHB, 5 * UC_CHB, BAR(B_UFULL));
      TSW(6);
#pragma unroll 1
      for (int i = lane; i < 135; i += 32) sts128(work + TA01A + 16 * i + (i < 81 ? 0 : 67 * 144), 0u, 0u, 0u, 0u);
      mbar_wait(BAR(B_KF + 2), 0);
#pragma unroll 1
      for (int k = lane; k < 67; k += 32) table(k, sb + OFF_KC, TA01A, 1u);
      fence_async_smem();
      __syncwarp();
      if (lane == 0) mbar_arrive(BAR(B_URDY));
      TSW(7);

      if (lane == 0) {
#pragma unroll
        for (int c = 0; c < 3; c++) {
          mbar_wait(BAR(B_HST + c), 0);
          tma2d_store(&tm_hld, sb + ((10 + c) % 3) * STAGE_BYTES, 192 * j + 64 * c, 128 * m);
          if (c == 2) bulk_s2g(g_gate + (2 * m + kh) * 256 + 64 * nt, sb + OFF_GOUT, 256);
          bulk_commit();
        }
        asm volatile("cp.async.bulk.wait_group 2;" ::: "memory");
        flag_add(&g_hflag[(m * 24 + j * 3) * 8]);
        asm volatile("cp.async.bulk.wait_group 1;" ::: "memory");
        flag_add(&g_hflag[(m * 24 + j * 3 + 1) * 8]);
        asm volatile("cp.async.bulk.wait_group 0;" ::: "memory");
        flag_add(&g_hflag[(m * 24 + j * 3 + 2) * 8]);
      }
      __syncwarp();
      const unsigned* fl = &g_hflag[(m * 24 + (kcoord(3 + (lane < 9 ? lane : 0)) >> 6)) * 8];
      bool rdy = lane >= 9;
      uint32_t mask = 0;
      int slot = 1;
#pragma unroll 1
      for (int q = 0; q < 9; q++) {
        const int kk = kcoord(3 + q);
#pragma unroll 1
        for (uint32_t i = 0; !((mask >> q) & 1); i++) {
          if (!rdy) rdy = flag_try(fl, epoch1) || i > (1u << 20);
          mask = __ballot_sync(0xffffffffu, rdy);
        }
          asm volatile("{\n.reg .pred p;\nelect.sync _|p, 0xffffffff;\nbar.sync %5, 288;\n"
                       "@p cp.async.bulk.tensor.2d.shared::cluster.global.mbarrier::complete_tx::bytes [%0], [%1, {%3, %4}], [%2];\n}\n"
                       ::"r"(sb + slot * STAGE_BYTES), "l"(&tm_hld), "r"(BAR(B_FULL + slot)), "r"(kk), "r"(128 * m), "r"(11 + slot) : "memory");
        if (++slot == 3) slot = 0;
      }
      if (lane == 0) {
        mbar_expect_tx(BAR(B_G), 1024);
        bulk_g2s(sb + OFF_GW, g_gate + (2 * m + kh) * 256, 1024, BAR(B_G));
      }
    }
  } else if (warp < 8) {
    const int wg = warp >> 2, w = warp & 3, wt = tid & 127, g = lane >> 2, t4 = lane & 3;
    const bool fin = (wg == kh);
    const uint32_t da0 = dlo(sb + wg * 8192, 16), db0 = dlo(sb + 16384, 8192), dg = dlo(sb + OFF_GW, 16);
    auto release = [&](int slot, int n) { bar_arrive(8 + slot, 288); if (n == 320) bar_arrive(11 + slot, 288); };
    auto release2 = [&](int slot, int it) {
      if (it < 20) release(slot, 320);
      else if (lane == 0) mbar_arrive_remote(mapa(BAR(B_PEERFREE), kh ^ 1));
    };
    {
      float acc[96];
#pragma unroll
      for (int i = 0; i < 24; i++) {
        const uint32_t bias = __float_as_uint(i < 12 ? v[i] : v1[i - 12]);
        acc[4 * i] = acc[4 * i + 2] = bf_lo(bias);
        acc[4 * i + 1] = acc[4 * i + 3] = bf_hi(bias);
      }
      float gc[4] = {0.f, 0.f, 0.f, 0.f};
      reg_fence(gc);
      reg_fence(acc);
      int slot = 0, ph = 0;
#pragma unroll 1
      for (int it = 0; it < 10; it++) {
        const uint32_t da = da0 + slot * (STAGE_BYTES / 16), db = db0 + slot * (STAGE_BYTES / 16);
        mbar_wait(BAR(B_FULL + slot), ph);
        if (PRI & 8) mbar_wait(BAR(B_PRI), 1);
        TS(2 + it);
        if (fin && (it & 3) == nt) {
          wg_fence();
#pragma unroll
          for (int k = 0; k < 4; k++)
            wg_ss_n8(gc, dsc(da, k * 32, 1024, 1), dsc(dg + it * 8, k * 32, 128, 0), 1);
          wg_commit();
        }
#pragma unroll
        for (int k = 0; k < 4; k++) {
          if (k % SPLIT == 0) wg_fence();
          wg_ss_n192(acc, dsc(da, k * 32, 1024, 1), dsc(db, k * 2048, 1024, 1), 1);
          if (k % SPLIT == SPLIT - 1) {
            wg_commit();
            wg_wait<1>();
            if (k == SPLIT - 1 && it > 0) release(slot == 0 ? 2 : slot - 1, 288);
          }
        }
        if (++slot == 3) { slot = 0; ph ^= 1; }
      }
      wg_wait<0>();
      reg_fence(acc);
      release(0, 288);
      reg_fence(gc);
      if (fin && t4 == 0) { sts_f(sb + OFF_GOUT + 4 * (16 * w + g), gc[0]); sts_f(sb + OFF_GOUT + 4 * (16 * w + g + 8), gc[2]); }
      TS(12);
      const int mi = lane >> 3;
      const int srow = 64 * wg + 16 * w + (mi & 1) * 8 + (lane & 7);
      const uint32_t dbase = sb + srow * 128;
#pragma unroll
      for (int i = 0; i < 24; i += 2) {
        const int c = i >> 3, grp = (i & 7) + (mi >> 1);
        stmatrix4(dbase + ((10 + c) % 3) * STAGE_BYTES + ((grp ^ (lane & 7)) << 4),
                  relu_sq_bf16(acc[4 * i], acc[4 * i + 1]), relu_sq_bf16(acc[4 * i + 2], acc[4 * i + 3]),
                  relu_sq_bf16(acc[4 * i + 4], acc[4 * i + 5]), relu_sq_bf16(acc[4 * i + 6], acc[4 * i + 7]));
        if ((i & 7) == 6) {
          fence_async_smem();
          __syncwarp();
          if (lane == 0) mbar_arrive(BAR(B_HST + c));
        }
      }
    }
    TS(13);
    asm volatile("barrier.cluster.wait.aligned;" ::: "memory");
    float acc[80];
    const int to = 4 * (nt & 1);
    const uint32_t bmask = fin ? 0u : 0xffff0000u, b2a = sb + OFF_B2 + 16 * to + 4 * t4, b2b = sb + OFF_B2 - 64 * to + 4 * t4;
#pragma unroll
    for (int i = 0; i < 20; i++) {
      const uint32_t v = lds32((i < 16 ? b2a : b2b) + 16 * i);
      acc[4 * i] = acc[4 * i + 2] = __uint_as_float((v << 16) & bmask);
      acc[4 * i + 1] = acc[4 * i + 3] = __uint_as_float(v & bmask);
    }
    reg_fence(acc);
    float g0 = 0.f, g1 = 0.f;
    {
      int slot = 1, ph = 1;
#pragma unroll 1
      for (int kb = 0; kb < 12; kb++) {
        const int it = 10 + kb;
        const uint32_t da = da0 + slot * (STAGE_BYTES / 16), db = db0 + slot * (STAGE_BYTES / 16);
        bool pend = kb > 0 && it <= 20;
        if (kb == 3 || (fin && it == GATE_FIN)) {
          wg_wait<0>();
          if (pend) release2(slot == 0 ? 2 : slot - 1, it);
          pend = false;
          if (kb != 3) {
      mbar_wait(BAR(B_G), 0);
      g0 = lds_f(sb + OFF_GW + 256 * t4 + 4 * (16 * w + g)); g1 = lds_f(sb + OFF_GW + 256 * t4 + 4 * (16 * w + g + 8));
      g0 += __shfl_xor_sync(0xffffffffu, g0, 1); g1 += __shfl_xor_sync(0xffffffffu, g1, 1);
      g0 += __shfl_xor_sync(0xffffffffu, g0, 2); g1 += __shfl_xor_sync(0xffffffffu, g1, 2);
      g0 = __fdividef(1.f, 1.f + __expf(-g0)); g1 = __fdividef(1.f, 1.f + __expf(-g1));
            bar_sync(5, 256);
          }
        }
        mbar_wait(BAR(B_FULL + slot), ph);
        if (PRI && kb >= PRIK && (!(PRI & 16) || fin)) mbar_wait(BAR(B_PRI), 1);
        TS(14 + kb);
#pragma unroll
        for (int k = 0; k < 4; k++) {
          if (k % SPLIT == 0) wg_fence();
          wg_ss_n160(acc, dsc(da, k * 32, 1024, 1), dsc(db, k * 2048, 1024, 1), 1);
          if (k % SPLIT == SPLIT - 1) {
            wg_commit();
            wg_wait<1>();
            if (k == SPLIT - 1 && pend) release2(slot == 0 ? 2 : slot - 1, it);
          }
        }
        if (++slot == 3) { slot = 0; ph ^= 1; }
      }
    }
    if (!fin) bar_arrive(5, 256);
    const int mi = lane >> 3, lr = lane & 7;
    if (!fin) {
      mbar_wait(BAR(B_PEERFREE), 0);
      if (PRIL & 2) mbar_wait(BAR(B_PRI), 1);
      wg_wait<0>();
      reg_fence(acc);
      TS(26);
      const uint32_t rbuf = mapa(sb + OFF_Q + wt * 16, kh ^ 1), rbar = mapa(BAR(B_RED), kh ^ 1);
#pragma unroll
      for (int i = 0; i < 20; i++) st_async128(rbuf + i * 2048, acc[4 * i], acc[4 * i + 1], acc[4 * i + 2], acc[4 * i + 3], rbar);
      TS(27);
    } else {
      const float h0 = 1.f - g0, h1 = 1.f - g1;
      const int row = 16 * w + (mi & 1) * 8 + lr;
      const uint32_t ot = sb + OFF_OUT + row * 64 + (((mi >> 1) ^ ((row >> 1) & 3)) << 4);
      const uint32_t at = sb + OFF_AT + (8 * (mi >> 1) + lr) * 128 + (((2 * w + (mi & 1)) ^ lr) << 4);
      const uint32_t gp[2] = {pack_bf16(g0, g0), pack_bf16(g1, g1)};
      mbar_wait(BAR(B_RED), 0);
      wg_wait<0>();
      reg_fence(acc);
      TS(26);
      uint32_t r[40];
#pragma unroll
      for (int i = 0; i < 20; i++) {
        const float4 v = lds128f(sb + OFF_Q + wt * 16 + i * 2048);
        r[2 * i] = pack_bf16((acc[4 * i] + v.x) * h0, (acc[4 * i + 1] + v.y) * h0);
        r[2 * i + 1] = pack_bf16((acc[4 * i + 2] + v.z) * h1, (acc[4 * i + 3] + v.w) * h1);
      }
      reg_fence_u(r);
      TS(27);
      mbar_wait(BAR(B_AT), 0);
      TS(28);
      uint32_t a[40];
#pragma unroll
      for (int i = 0; i < 20; i += 2)
        ldmatrix4t(at + (i < 16 ? to : -4 * to) * 1024 + i * 1024, a[2 * i], a[2 * i + 1], a[2 * i + 2], a[2 * i + 3]);
#pragma unroll
      for (int i = 0; i < 20; i += 2) {
#pragma unroll
        for (int q = 0; q < 4; q++)
          asm("fma.rn.bf16x2 %0, %1, %2, %0;" : "+r"(r[2 * i + q]) : "r"(gp[q & 1]), "r"(a[2 * i + q]));
        stmatrix4((ot ^ ((i & 2) << 4)) + (i < 16 ? to : -4 * to) * 1024 + (i >> 2) * 4096, r[2 * i], r[2 * i + 1], r[2 * i + 2], r[2 * i + 3]);
      }
      fence_async_smem();
      bar_sync(1 + wg, 128);
      if (wt == 0) {
        tma3d_store(&tm_out, sb + OFF_OUT, 0, 128 * m + 64 * kh, 5 * nt);
        bulk_commit();
        asm volatile("cp.async.bulk.wait_group.read 0;" ::: "memory");
      }
      TS(29);
    }
    TSDUMP();
  } else {

    const int wt = tid & 127, w = warp & 3;
    if (lane == 0) mbar_arrive(BAR(B_WE));
    if (w >= 2) {
#pragma unroll
      for (int i = 0; i < 3; i++) sts128f(sb + OFF_SOUT + i * 1024 + (wt & 63) * 16, d[12 + 4 * i], d[13 + 4 * i], d[14 + 4 * i], d[15 + 4 * i]);
    }
    TS(14);
    const uint32_t dta = dlo(work, 288);
    const int mi = lane >> 3, lr = lane & 7, rho = 8 * (3 - w) + lr;
    mbar_wait(BAR(B_UFULL), 0);
    mbar_wait(BAR(B_URDY), 0);
    float acc[32], a2[24], a3[16], s[16];
#pragma unroll
    for (int i = 0; i < 32; i++) acc[i] = 0.f;
#pragma unroll
    for (int i = 0; i < 24; i++) a2[i] = 0.f;
#pragma unroll
    for (int i = 0; i < 16; i++) { a3[i] = 0.f; s[i] = d[i]; }
    reg_fence(acc); reg_fence(a2); reg_fence(a3);
    const uint32_t so = sb + OFF_SOUT + (4 * mi + (lr >> 1)) * 128 + (((4 * (lr & 1) + 3 - w) ^ (4 * (mi & 1) + (lr >> 1))) << 4);
    const uint32_t ya = work + Y2 + (rho & 3) * YC + (16 + 8 * mi + (rho >> 2)) * 16;
    const uint32_t yb = work + Y3 + (2 * (rho & 1) + (mi >> 1)) * YC + (32 + 16 * (mi & 1) + (rho >> 1)) * 16;
    const uint32_t yl = work + Y2 + (3 - w) * YC + lane * 16;
#pragma unroll 1
    for (int c = 0; c < 6; c++) {
      const uint32_t kc = sb + OFF_KC + c * KC_CHB;
      const uint32_t wa = work + ((c & 1) ? 0 : WD1), wb = work + ((c & 1) ? 0 : WD2);
      if (c > 0) {
      if (wt == 0) asm volatile("cp.async.bulk.wait_group.read 0;" ::: "memory");
      bar_sync(3, 128);
        uint32_t t[10];
        ldmatrix4t(yl + 256, t[0], t[1], t[2], t[3]);
        asm volatile("ldmatrix.sync.aligned.m8n8.x2.trans.shared.b16 {%0,%1}, [%2];" : "=r"(t[4]), "=r"(t[5]) : "r"(yl + 768) : "memory");
        ldmatrix4t(yl + (Y3 - Y2) + 512, t[6], t[7], t[8], t[9]);
#pragma unroll
        for (int i = 0; i < 6; i++) { s[4 + 2 * i] += bf_lo(t[i]); s[5 + 2 * i] += bf_hi(t[i]); }
#pragma unroll
        for (int i = 0; i < 4; i++) { s[8 + 2 * i] += bf_lo(t[6 + i]); s[9 + 2 * i] += bf_hi(t[6 + i]); }
        stmatrix4t(so, pack_bf16(s[0], s[1]), pack_bf16(s[2], s[3]), pack_bf16(s[4], s[5]), pack_bf16(s[6], s[7]));
        stmatrix4t(so + 2048, pack_bf16(s[8], s[9]), pack_bf16(s[10], s[11]), pack_bf16(s[12], s[13]), pack_bf16(s[14], s[15]));
      fence_async_smem();
      __syncwarp();
      if (lane == 0) mbar_arrive(BAR(B_OUT));
      }
      if (c < 5) {
        if (c > 0) mbar_wait(BAR((c & 1) ? B_WF : B_WG), (c - 1) >> 1);
        const uint32_t da = dta + ((c & 1) ? 0 : TA01A / 16), du = dlo(sb + OFF_UC + c * UC_CHB + 16, UC_C);
        if ((PRI & 5) && wt == 0) mbar_arrive(BAR(B_PRI));
        wg_fence();
#pragma unroll
        for (int k = 0; k < 19; k++)
          wg_ss_n64_k(acc, dsc(da, k * 576, 144, 0), dsc(du, ((k + 1) & 1) * 2 * UC_C + ((k + 1) >> 1) * 16, 128, 0), k != 0);
        wg_commit();
        if ((PRI & 1) && wt == 0) mbar_arrive(BAR(B_PRI));
        TS(15 + 3 * c);
      }
      if (c == 0) {
      bar_sync(3, 128);
        if (w < 2) {
#pragma unroll
          for (int i = 0; i < 3; i++) {
            const float4 x = lds128f(sb + OFF_SOUT + i * 1024 + wt * 16);
            v[4 * i] = s[4 * i] + x.x; v[4 * i + 1] = s[4 * i + 1] + x.y; v[4 * i + 2] = s[4 * i + 2] + x.z; v[4 * i + 3] = s[4 * i + 3] + x.w;
          }
          scatter(4);
        } else {
          const int z = wt & 63;
          auto zf = [&](int off, int n) {
#pragma unroll
            for (int i = 0; i < n; i += 64)
              if (i + 64 <= n || z < n - i) sts128(work + off + 16 * (i + z), 0u, 0u, 0u, 0u);
          };
          zf(0, 81); zf(76 * 144, 108); zf(TA2 + 16 * 144, 108); zf(TA2 + 3168 + 16 * 144, 54);
          if (z < 48) sts128(work + TA3 + (z / 24) * 2016 + (8 + 2 * ((z % 24) >> 3)) * 144 + (z & 7) * 16, 0u, 0u, 0u, 0u);
        }
      fence_async_smem();
      __syncwarp();
      if (lane == 0) mbar_arrive(BAR(B_OUT));
      }
      uint32_t wc[4];
      float k1024;
      if (c < 5) {
        if (c == 0) mbar_wait(BAR(B_OUT), 0);
        mbar_wait(BAR(B_WF + 1), c & 1);
        TS(16 + 3 * c);
        if ((PRI & 2) && wt == 0) mbar_arrive(BAR(B_PRI));
        ldmatrix4(wb + WC + (mi >> 1) * 1024 + (32 * (mi & 1) + rho) * 16, wc[0], wc[1], wc[2], wc[3]);
        k1024 = bf_lo(lds16(kc + 2 * 584));
        const uint32_t dwa = dlo(wa + W5, 128), dwb = dlo(wb + W9, 128);
        wg_fence();
#pragma unroll
        for (int k = 0; k < 8; k++)
          wg_ss_n48_t(a2, dsc(dta, TA2 + (k >> 2) * 3168 + (k & 3) * 576, 144, 0), dsc(dwa, (k >> 2) * 3584 + (k & 3) * 256, 512, 0), k != 0);
#pragma unroll
        for (int k = 0; k < 4; k++)
          wg_ss_n32_t(a3, dsc(dta, TA3 + (k >> 1) * 2016 + (k & 1) * 576, 144, 0), dsc(dwb, (k >> 1) * 2048 + (k & 1) * 256, 512, 0), k != 0);
        wg_commit();
        if ((PRI & 2) && wt == 0) mbar_arrive(BAR(B_PRI));
      }
      mbar_wait(BAR(B_OUT), c & 1);
      if (wt == 0 && c > 0) { tma2d_store(&tm_ast, sb + OFF_SOUT, 0, 32 * (5 * b + c - 1)); bulk_commit(); }
      wg_wait<0>();
      reg_fence(acc); reg_fence(a2); reg_fence(a3);
      if ((PRI & 4) && wt == 0 && c != (PRIL ? 4 : 5)) mbar_arrive(BAR(B_PRI));
      if (c == 5) break;
      TS(17 + 3 * c);
      if (lane == 0) mbar_arrive(BAR(B_WE));
      uint32_t y[6];
      y[0] = pack_bf16(a2[0], a2[1]);
#pragma unroll
      for (int i = 1; i < 6; i++) y[i] = pack_bf16(a2[4 * i] + a2[4 * i - 2], a2[4 * i + 1] + a2[4 * i - 1]);
      stmatrix4(ya, y[0], y[1], y[2], y[3]);
      asm volatile("stmatrix.sync.aligned.m8n8.x2.shared.b16 [%0], {%1,%2};" ::"r"(ya + 512), "r"(y[4]), "r"(y[5]) : "memory");
#pragma unroll
      for (int i = 0; i < 4; i++) {
        float f0 = fmaf(k1024, bf_lo(wc[i]), a3[4 * i]), f1 = fmaf(k1024, bf_hi(wc[i]), a3[4 * i + 1]);
        if (i & 1) { f0 += a3[4 * i - 2]; f1 += a3[4 * i - 1]; }
        y[i] = pack_bf16(f0, f1);
      }
      stmatrix4(yb, y[0], y[1], y[2], y[3]);
      s[0] = acc[0]; s[1] = acc[1];
#pragma unroll
      for (int i = 1; i < 8; i++) { s[2 * i] = acc[4 * i] + acc[4 * i - 2]; s[2 * i + 1] = acc[4 * i + 1] + acc[4 * i - 1]; }
      reg_fence(s);
    }
    if (wt == 0) {
      bulk_wait0();
      flag_add(&g_aflag[(b >> 5) * 32]);
      mbar_arrive(BAR(B_SSMDONE));
    }
    TS(30);

    TSDUMP();
  }
}

typedef CUresult (*EncodeFn)(CUtensorMap*, CUtensorMapDataType, cuuint32_t, void*, const cuuint64_t*, const cuuint64_t*,
                             const cuuint32_t*, const cuuint32_t*, CUtensorMapInterleave, CUtensorMapSwizzle,
                             CUtensorMapL2promotion, CUtensorMapFloatOOBfill);

void encode(EncodeFn fn, CUtensorMap* tm, void* ptr, int rank, const cuuint64_t* dims, const cuuint64_t* strides,
            const cuuint32_t* box, CUtensorMapSwizzle sw) {
  const cuuint32_t es[3] = {1, 1, 1};
  fn(tm, CU_TENSOR_MAP_DATA_TYPE_BFLOAT16, rank, ptr, dims, strides, box, es, CU_TENSOR_MAP_INTERLEAVE_NONE, sw,
     CU_TENSOR_MAP_L2_PROMOTION_L2_128B, CU_TENSOR_MAP_FLOAT_OOB_FILL_NONE);
}

}

extern "C" void kernel_launch(void* const* d_in, const int* in_sizes, int n_in, void* d_out, int out_size) {
  static EncodeFn fn = nullptr;
  static void *ph = nullptr, *paT = nullptr, *puT = nullptr;
  static int nsm = 0;
  if (!fn) {
    void* f = nullptr;
    cudaDriverEntryPointQueryResult qr;
    cudaGetDriverEntryPoint("cuTensorMapEncodeTiled", &f, cudaEnableDefault, &qr);
    fn = (EncodeFn)f;
    cudaGetSymbolAddress(&ph, g_h);
    cudaGetSymbolAddress(&paT, g_aT);
    cudaGetSymbolAddress(&puT, g_uT);
    cudaFuncSetAttribute(fused_kernel, cudaFuncAttributeMaxDynamicSharedMemorySize, SMEM_BYTES);
    int dev = 0;
    cudaGetDevice(&dev);
    cudaDeviceGetAttribute(&nsm, cudaDevAttrMultiProcessorCount, dev);
  }
  CUtensorMap tm_x, tm_w1, tm_hld, tm_w2a, tm_w2b, tm_u, tm_aT, tm_out, tm_ust, tm_ast;
  {
    const cuuint64_t d[2] = {DM, SEQ}, s[1] = {DM * 2};
    const cuuint32_t bx[2] = {64, 128}, bu[2] = {40, 256};
    encode(fn, &tm_x, d_in[0], 2, d, s, bx, CU_TENSOR_MAP_SWIZZLE_128B);
    encode(fn, &tm_u, d_in[0], 2, d, s, bu, CU_TENSOR_MAP_SWIZZLE_NONE);
  }
  {
    const cuuint64_t d[3] = {64, DM, FF / 64}, s[2] = {FF * 2, 128};
    const cuuint32_t bx[3] = {64, 64, 3};
    encode(fn, &tm_w1, d_in[10], 3, d, s, bx, CU_TENSOR_MAP_SWIZZLE_128B);
  }
  {
    const cuuint64_t d[2] = {FF, SEQ}, s[1] = {FF * 2};
    const cuuint32_t b2[2] = {64, 128};
    encode(fn, &tm_hld, ph, 2, d, s, b2, CU_TENSOR_MAP_SWIZZLE_128B);
  }
  {
    const cuuint64_t d[3] = {64, FF, DM / 64}, s[2] = {DM * 2, 128};
    const cuuint32_t bx[3] = {64, 64, 2};
    encode(fn, &tm_w2a, d_in[12], 3, d, s, bx, CU_TENSOR_MAP_SWIZZLE_128B);
    const cuuint64_t d2[2] = {DM, FF};
    encode(fn, &tm_w2b, d_in[12], 2, d2, s, bx, CU_TENSOR_MAP_SWIZZLE_128B);
  }
  {
    const cuuint64_t d[2] = {SEQ, DM}, s[1] = {SEQ * 2};
    const cuuint32_t bx[2] = {64, 160};
    encode(fn, &tm_aT, paT, 2, d, s, bx, CU_TENSOR_MAP_SWIZZLE_128B);
  }
  {
    const cuuint64_t d[3] = {32, SEQ, DM / 32}, s[2] = {DM * 2, 64};
    const cuuint32_t bx[3] = {32, 64, 5};
    encode(fn, &tm_out, d_out, 3, d, s, bx, CU_TENSOR_MAP_SWIZZLE_64B);
  }
  {
    const cuuint64_t d[3] = {16, DM * 4, 32}, s[2] = {UC_C, 32};
    const cuuint32_t bx[3] = {16, 160, 1};
    encode(fn, &tm_ust, (char*)puT + 160, 3, d, s, bx, CU_TENSOR_MAP_SWIZZLE_32B);
    const cuuint64_t d2[2] = {64, DM * 32}, s2[1] = {128};
    const cuuint32_t b2[2] = {64, 32};
    encode(fn, &tm_ast, paT, 2, d2, s2, b2, CU_TENSOR_MAP_SWIZZLE_128B);
  }

  Params P;
  P.x = (const __nv_bfloat16*)d_in[0];
  P.Are = (const __nv_bfloat16*)d_in[1]; P.Aim = (const __nv_bfloat16*)d_in[2];
  P.Bre = (const __nv_bfloat16*)d_in[3]; P.Bim = (const __nv_bfloat16*)d_in[4];
  P.Cre = (const __nv_bfloat16*)d_in[5]; P.Cim = (const __nv_bfloat16*)d_in[6];
  P.logdt = (const __nv_bfloat16*)d_in[7]; P.Dskip = (const __nv_bfloat16*)d_in[8];
  P.b1 = (const __nv_bfloat16*)d_in[11]; P.b2 = (const __nv_bfloat16*)d_in[13]; P.gw = (const __nv_bfloat16*)d_in[14];
  P.w2 = (const __nv_bfloat16*)d_in[12]; P.w1 = (const __nv_bfloat16*)d_in[10];
  P.use_smid = nsm == 132;
  fused_kernel<<<P.use_smid ? 132 : NCTA, NTHREADS, SMEM_BYTES, cudaStreamPerThread>>>(tm_x, tm_w1, tm_hld, tm_w2a, tm_w2b, tm_u, tm_aT, tm_out, tm_ust, tm_ast, P);
}
```
